```python
import torch

def _softmax(x, axis=-1):
    return torch.softmax(x, dim=axis)
def _gelu(x):
    return torch.nn.functional.gelu(x, approximate="tanh")
def _silu(x):
    return torch.nn.functional.silu(x)
def _sigmoid(x):
    return torch.sigmoid(x)
def _layernorm(x, axis=-1, eps=1e-5):
    m = x.mean(dim=axis, keepdim=True)
    v = x.var(dim=axis, keepdim=True, unbiased=False)
    return (x - m) / torch.sqrt(v + eps)
def _scatter_add(tgt, idx, src, axis=0):
    return tgt.clone().index_add_(axis, idx, src)
def _segment_sum(src, seg, n):
    out = torch.zeros((n,) + src.shape[1:], dtype=src.dtype)
    return out.index_add_(0, seg, src)
def _pad(x, pw):
    flat = tuple(v for pair in reversed(pw) for v in pair)
    return torch.nn.functional.pad(x, flat)

kernel_name = 'parallel_sum__ssm_conv_s5__dense_activation_mish__prompt'

def setup_inputs():

    _w = (lambda a: (lambda t: t.to(torch.bfloat16) if t.is_floating_point() else t)(torch.as_tensor(a)))
    def _A_setup():
        B, S, D = 1, 2048, 512
        P = D
        Lambda_re = -0.5 * (lambda _x: torch.exp(torch.as_tensor(_x)))((lambda *s: torch.randn(*s, dtype=torch.bfloat16) * 0.2)(P))
        Lambda_im = (lambda *s: torch.randn(*s, dtype=torch.bfloat16) * 0.8)(P) * 1.0
        B_re = (lambda *s: torch.randn(*s, dtype=torch.bfloat16) * 0.2)(P, D) * (D ** -0.5)
        B_im = (lambda *s: torch.randn(*s, dtype=torch.bfloat16) * 0.2)(P, D) * (D ** -0.5)
        C_re = (lambda *s: torch.randn(*s, dtype=torch.bfloat16) * 0.2)(D, P) * (P ** -0.5)
        C_im = (lambda *s: torch.randn(*s, dtype=torch.bfloat16) * 0.2)(D, P) * (P ** -0.5)
        log_dt = (lambda *s: torch.randn(*s, dtype=torch.bfloat16) * 0.2)(P) * 0.3 - 2.0
        Dskip = (lambda *s: torch.randn(*s, dtype=torch.bfloat16) * 0.05)(D)
        return {
            "x": _w((lambda *s: torch.randn(*s, dtype=torch.bfloat16) * 0.05)(B, S, D)),
            "Lambda_re": _w(Lambda_re),
            "Lambda_im": _w(Lambda_im),
            "B_re": _w(B_re),
            "B_im": _w(B_im),
            "C_re": _w(C_re),
            "C_im": _w(C_im),
            "log_dt": _w(log_dt),
            "Dskip": _w(Dskip),
        }
    _A_in = _A_setup()

    def _B_setup():
        B, S, D, F = 1, 2048, 512, 1376
        return {
            "x": _w((lambda *s: torch.randn(*s, dtype=torch.bfloat16) * 0.05)(B, S, D)),
            "w1": _w((lambda *s: torch.randn(*s, dtype=torch.bfloat16) * 0.8)(D, F) * (D ** -0.5)),
            "b1": _w((lambda *s: torch.randn(*s, dtype=torch.bfloat16) * 0.2)(F)),
            "w2": _w((lambda *s: torch.randn(*s, dtype=torch.bfloat16) * 0.2)(F, D) * (F ** -0.5)),
        }
    _B_in = _B_setup()

    return {
        "A_x": _A_in["x"],
        "A_Lambda_re": _A_in["Lambda_re"],
        "A_Lambda_im": _A_in["Lambda_im"],
        "A_B_re": _A_in["B_re"],
        "A_B_im": _A_in["B_im"],
        "A_C_re": _A_in["C_re"],
        "A_C_im": _A_in["C_im"],
        "A_log_dt": _A_in["log_dt"],
        "A_Dskip": _A_in["Dskip"],
        "B_x": _B_in["x"],
        "B_w1": _B_in["w1"],
        "B_b1": _B_in["b1"],
        "B_w2": _B_in["w2"],
    }

def reference(A_x, A_Lambda_re, A_Lambda_im, A_B_re, A_B_im, A_C_re, A_C_im, A_log_dt, A_Dskip, B_x, B_w1, B_b1, B_w2):
    def _A_ref(x, Lambda_re, Lambda_im, B_re, B_im, C_re, C_im, log_dt, Dskip):
        Bsz, L, H = x.shape
        Lam = Lambda_re + 1j * Lambda_im
        Bmat = B_re + 1j * B_im
        Cmat = C_re + 1j * C_im
        dt = torch.exp(log_dt)
        Lam_bar = torch.exp(dt * Lam)
        B_bar = ((Lam_bar - 1.0) / Lam)[:, None] * Bmat
        Bu = torch.einsum("bld,pd->blp", x + 0j, B_bar)
        h = torch.zeros_like(Bu[:, 0, :])
        hs = []
        for t in range(L):
            h = Lam_bar[None, :] * h + Bu[:, t, :]
            hs.append(h)
        hseq = torch.stack(hs, 1)
        y = 2.0 * torch.einsum("blp,dp->bld", hseq, Cmat).real + x * Dskip[None, None, :]
        return y

    def _B_ref(x, w1, b1, w2):
        h = torch.einsum("bsd,df->bsf", x, w1) + b1
        sp = torch.log1p(torch.exp(-torch.abs(h))) + torch.where(h > 0, h, torch.zeros_like(h))
        act = h * torch.tanh(sp)
        return torch.einsum("bsf,fd->bsd", act, w2)

    x = A_x
    xn = _layernorm(x, axis=-1)
    return x + _A_ref(xn, A_Lambda_re, A_Lambda_im, A_B_re, A_B_im, A_C_re, A_C_im, A_log_dt, A_Dskip) + _B_ref(xn, B_w1, B_b1, B_w2)
```

```cpp
#include <cuda_runtime.h>
#include <cuda_bf16.h>
#include <cuda.h>
#include <stdint.h>
#include <type_traits>

typedef __nv_bfloat16 bf16;

constexpr int DM = 512, PS = 512, FF = 1376;
constexpr int BM = 128, CHN = 64, FFP = 176;
constexpr int NST = 4, SLOT = 20480;
constexpr int NST2 = 5, SLOT2 = 24576;
constexpr int OFF_X = 0;
constexpr int OFF_HP = 0;
constexpr int OFF_BU = 32768;
constexpr int OFF_RING2 = 98304;
constexpr int OFF_RING = 147456;
constexpr int OFF_MISC = OFF_RING + NST * SLOT;
constexpr int OFF_BARS = OFF_MISC;
constexpr int OFF_CC = OFF_MISC + 256;
constexpr int OFF_LB = OFF_CC + 512;
constexpr int OFF_B1 = OFF_LB + 512;
constexpr int OFF_E0 = 221184;
constexpr int OFF_SUM = OFF_BU;
constexpr int OFF_EPOCH = OFF_B1 + 704;
constexpr int SMEM_BYTES = OFF_EPOCH + 16;

__device__ bf16 g_xn[2048 * 512];
__device__ uint4 g_part[16 * 8 * 8 * 256 * 4];
__device__ float2 g_E[16 * 512];
__device__ unsigned g_epoch[128];

#define TSTAMP(i)
__device__ __forceinline__ uint32_t smem_u32(const void* p) { return (uint32_t)__cvta_generic_to_shared(p); }
__device__ __forceinline__ void mbar_init(uint32_t a, int c) { asm volatile("mbarrier.init.shared::cta.b64 [%0], %1;" ::"r"(a), "r"(c)); }
__device__ __forceinline__ void mbar_expect_tx(uint32_t a, int b) { asm volatile("mbarrier.arrive.expect_tx.shared::cta.b64 _, [%0], %1;" ::"r"(a), "r"(b) : "memory"); }
__device__ __forceinline__ void mbar_arrive(uint32_t a) { asm volatile("mbarrier.arrive.shared::cta.b64 _, [%0];" ::"r"(a) : "memory"); }
__device__ __forceinline__ void mbar_wait(uint32_t a, int ph) {
  uint32_t ok = 0;
#pragma unroll 1
  for (uint32_t it = 0; it < (1u << 26); ++it) {
    asm volatile("{\n.reg .pred p;\nmbarrier.try_wait.parity.shared::cta.b64 p, [%1], %2;\nselp.u32 %0, 1, 0, p;\n}" : "=r"(ok) : "r"(a), "r"(ph) : "memory");
    if (ok) return;
  }
  __trap();
}
__device__ __forceinline__ void tma_2d(uint32_t dst, const CUtensorMap* tm, int c0, int c1, uint32_t bar) {
  asm volatile("cp.async.bulk.tensor.2d.shared::cluster.global.mbarrier::complete_tx::bytes [%0], [%1, {%3, %4}], [%2];" ::"r"(dst), "l"((uint64_t)tm), "r"(bar), "r"(c0), "r"(c1) : "memory");
}
__device__ __forceinline__ void fence_async_all() { asm volatile("fence.proxy.async;" ::: "memory"); }
template <int ID, int N> __device__ __forceinline__ void bar_sync() { asm volatile("bar.sync %0, %1;" ::"n"(ID), "n"(N) : "memory"); }
template <int ID, int N> __device__ __forceinline__ void bar_arrive() { asm volatile("bar.arrive %0, %1;" ::"n"(ID), "n"(N) : "memory"); }
__device__ __forceinline__ void wg_fence() { asm volatile("wgmma.fence.sync.aligned;" ::: "memory"); }
__device__ __forceinline__ void wg_commit() { asm volatile("wgmma.commit_group.sync.aligned;" ::: "memory"); }
template <int N> __device__ __forceinline__ void wg_wait() { asm volatile("wgmma.wait_group.sync.aligned %0;" ::"n"(N) : "memory"); }
__device__ __forceinline__ uint64_t mk_desc(uint32_t addr, uint32_t lbo, uint32_t sbo, uint32_t mode) {
  return (uint64_t)((addr & 0x3FFFF) >> 4) | ((uint64_t)(lbo >> 4) << 16) | ((uint64_t)(sbo >> 4) << 32) | ((uint64_t)mode << 62);
}
__device__ __forceinline__ float bf_lo(uint32_t u) { return __uint_as_float(u << 16); }
__device__ __forceinline__ float bf_hi(uint32_t u) { return __uint_as_float(u & 0xFFFF0000u); }
__device__ __forceinline__ uint32_t pack_bf(float lo, float hi) {
  uint32_t r; asm("cvt.rn.bf16x2.f32 %0, %1, %2;" : "=r"(r) : "f"(hi), "f"(lo)); return r;
}
__device__ __forceinline__ float rbf(float x) { return __uint_as_float(pack_bf(0.f, x) & 0xFFFF0000u); }
__device__ __forceinline__ unsigned ld_acquire(const unsigned* p) { unsigned v; asm volatile("ld.acquire.gpu.global.u32 %0, [%1];" : "=r"(v) : "l"(p) : "memory"); return v; }
__device__ __forceinline__ uint4 ld_relaxed_v4(const uint4* p) {
  uint4 v; asm volatile("ld.relaxed.gpu.global.v4.u32 {%0,%1,%2,%3}, [%4];" : "=r"(v.x), "=r"(v.y), "=r"(v.z), "=r"(v.w) : "l"(p) : "memory"); return v;
}

template<int TB, int SA>
__device__ __forceinline__ void wgmma_n128(float (&d)[64], uint64_t da, uint64_t db, int scaleD) {
  asm volatile("{\n.reg .pred p;\nsetp.ne.b32 p, %66, 0;\n"
    "wgmma.mma_async.sync.aligned.m64n128k16.f32.bf16.bf16 {%0, %1, %2, %3, %4, %5, %6, %7, %8, %9, %10, %11, %12, %13, %14, %15, %16, %17, %18, %19, %20, %21, %22, %23, %24, %25, %26, %27, %28, %29, %30, %31, %32, %33, %34, %35, %36, %37, %38, %39, %40, %41, %42, %43, %44, %45, %46, %47, %48, %49, %50, %51, %52, %53, %54, %55, %56, %57, %58, %59, %60, %61, %62, %63}, %64, %65, p, %67, 1, 0, %68;\n}\n"
    : "+f"(d[0]), "+f"(d[1]), "+f"(d[2]), "+f"(d[3]), "+f"(d[4]), "+f"(d[5]), "+f"(d[6]), "+f"(d[7]), "+f"(d[8]), "+f"(d[9]), "+f"(d[10]), "+f"(d[11]), "+f"(d[12]), "+f"(d[13]), "+f"(d[14]), "+f"(d[15]), "+f"(d[16]), "+f"(d[17]), "+f"(d[18]), "+f"(d[19]), "+f"(d[20]), "+f"(d[21]), "+f"(d[22]), "+f"(d[23]), "+f"(d[24]), "+f"(d[25]), "+f"(d[26]), "+f"(d[27]), "+f"(d[28]), "+f"(d[29]), "+f"(d[30]), "+f"(d[31]), "+f"(d[32]), "+f"(d[33]), "+f"(d[34]), "+f"(d[35]), "+f"(d[36]), "+f"(d[37]), "+f"(d[38]), "+f"(d[39]), "+f"(d[40]), "+f"(d[41]), "+f"(d[42]), "+f"(d[43]), "+f"(d[44]), "+f"(d[45]), "+f"(d[46]), "+f"(d[47]), "+f"(d[48]), "+f"(d[49]), "+f"(d[50]), "+f"(d[51]), "+f"(d[52]), "+f"(d[53]), "+f"(d[54]), "+f"(d[55]), "+f"(d[56]), "+f"(d[57]), "+f"(d[58]), "+f"(d[59]), "+f"(d[60]), "+f"(d[61]), "+f"(d[62]), "+f"(d[63])
    : "l"(da), "l"(db), "r"(scaleD), "n"(SA), "n"(TB));
}

template<int TB, int SA>
__device__ __forceinline__ void wgmma_n176(float (&d)[88], uint64_t da, uint64_t db, int scaleD) {
  asm volatile("{\n.reg .pred p;\nsetp.ne.b32 p, %90, 0;\n"
    "wgmma.mma_async.sync.aligned.m64n176k16.f32.bf16.bf16 {%0, %1, %2, %3, %4, %5, %6, %7, %8, %9, %10, %11, %12, %13, %14, %15, %16, %17, %18, %19, %20, %21, %22, %23, %24, %25, %26, %27, %28, %29, %30, %31, %32, %33, %34, %35, %36, %37, %38, %39, %40, %41, %42, %43, %44, %45, %46, %47, %48, %49, %50, %51, %52, %53, %54, %55, %56, %57, %58, %59, %60, %61, %62, %63, %64, %65, %66, %67, %68, %69, %70, %71, %72, %73, %74, %75, %76, %77, %78, %79, %80, %81, %82, %83, %84, %85, %86, %87}, %88, %89, p, %91, 1, 0, %92;\n}\n"
    : "+f"(d[0]), "+f"(d[1]), "+f"(d[2]), "+f"(d[3]), "+f"(d[4]), "+f"(d[5]), "+f"(d[6]), "+f"(d[7]), "+f"(d[8]), "+f"(d[9]), "+f"(d[10]), "+f"(d[11]), "+f"(d[12]), "+f"(d[13]), "+f"(d[14]), "+f"(d[15]), "+f"(d[16]), "+f"(d[17]), "+f"(d[18]), "+f"(d[19]), "+f"(d[20]), "+f"(d[21]), "+f"(d[22]), "+f"(d[23]), "+f"(d[24]), "+f"(d[25]), "+f"(d[26]), "+f"(d[27]), "+f"(d[28]), "+f"(d[29]), "+f"(d[30]), "+f"(d[31]), "+f"(d[32]), "+f"(d[33]), "+f"(d[34]), "+f"(d[35]), "+f"(d[36]), "+f"(d[37]), "+f"(d[38]), "+f"(d[39]), "+f"(d[40]), "+f"(d[41]), "+f"(d[42]), "+f"(d[43]), "+f"(d[44]), "+f"(d[45]), "+f"(d[46]), "+f"(d[47]), "+f"(d[48]), "+f"(d[49]), "+f"(d[50]), "+f"(d[51]), "+f"(d[52]), "+f"(d[53]), "+f"(d[54]), "+f"(d[55]), "+f"(d[56]), "+f"(d[57]), "+f"(d[58]), "+f"(d[59]), "+f"(d[60]), "+f"(d[61]), "+f"(d[62]), "+f"(d[63]), "+f"(d[64]), "+f"(d[65]), "+f"(d[66]), "+f"(d[67]), "+f"(d[68]), "+f"(d[69]), "+f"(d[70]), "+f"(d[71]), "+f"(d[72]), "+f"(d[73]), "+f"(d[74]), "+f"(d[75]), "+f"(d[76]), "+f"(d[77]), "+f"(d[78]), "+f"(d[79]), "+f"(d[80]), "+f"(d[81]), "+f"(d[82]), "+f"(d[83]), "+f"(d[84]), "+f"(d[85]), "+f"(d[86]), "+f"(d[87])
    : "l"(da), "l"(db), "r"(scaleD), "n"(SA), "n"(TB));
}

template<int TB, int SA>
__device__ __forceinline__ void wgmma_rs_n64(float (&d)[32], const uint32_t* a, uint64_t db, int scaleD) {
  asm volatile("{\n.reg .pred p;\nsetp.ne.b32 p, %37, 0;\n"
    "wgmma.mma_async.sync.aligned.m64n64k16.f32.bf16.bf16 {%0, %1, %2, %3, %4, %5, %6, %7, %8, %9, %10, %11, %12, %13, %14, %15, %16, %17, %18, %19, %20, %21, %22, %23, %24, %25, %26, %27, %28, %29, %30, %31}, {%32, %33, %34, %35}, %36, p, %38, 1, %39;\n}\n"
    : "+f"(d[0]), "+f"(d[1]), "+f"(d[2]), "+f"(d[3]), "+f"(d[4]), "+f"(d[5]), "+f"(d[6]), "+f"(d[7]), "+f"(d[8]), "+f"(d[9]), "+f"(d[10]), "+f"(d[11]), "+f"(d[12]), "+f"(d[13]), "+f"(d[14]), "+f"(d[15]), "+f"(d[16]), "+f"(d[17]), "+f"(d[18]), "+f"(d[19]), "+f"(d[20]), "+f"(d[21]), "+f"(d[22]), "+f"(d[23]), "+f"(d[24]), "+f"(d[25]), "+f"(d[26]), "+f"(d[27]), "+f"(d[28]), "+f"(d[29]), "+f"(d[30]), "+f"(d[31])
    : "r"(a[0]), "r"(a[1]), "r"(a[2]), "r"(a[3]), "l"(db), "r"(scaleD), "n"(SA), "n"(TB));
}

__device__ __forceinline__ uint32_t mish2_pack(float h0, float h1) {
  float e0, e1, rr;
  asm("ex2.approx.ftz.f32 %0, %1;" : "=f"(e0) : "f"(fminf(h0, 20.f) * 1.4426950408889634f));
  asm("ex2.approx.ftz.f32 %0, %1;" : "=f"(e1) : "f"(fminf(h1, 20.f) * 1.4426950408889634f));
  const float n0 = e0 * (e0 + 2.f), n1 = e1 * (e1 + 2.f);
  const float d0 = n0 + 2.f, d1 = n1 + 2.f;
  asm("rcp.approx.ftz.f32 %0, %1;" : "=f"(rr) : "f"(d0 * d1));
  return pack_bf((h0 * n0) * (rr * d1), (h1 * n1) * (rr * d0));
}

__global__ void __launch_bounds__(256) ln_kernel(const bf16* __restrict__ x) {
  asm volatile("griddepcontrol.launch_dependents;");
  const int lane = threadIdx.x & 31, row = blockIdx.x * 8 + (threadIdx.x >> 5);
  const uint4* xp = (const uint4*)(x + (size_t)row * DM);
  const uint4 xv0 = __ldg(xp + lane), xv1 = __ldg(xp + 32 + lane);
  float f[16];
  const uint32_t u[8] = {xv0.x, xv0.y, xv0.z, xv0.w, xv1.x, xv1.y, xv1.z, xv1.w};
#pragma unroll
  for (int j = 0; j < 8; ++j) { f[2 * j] = bf_lo(u[j]); f[2 * j + 1] = bf_hi(u[j]); }
  float sum = 0.f;
#pragma unroll
  for (int j = 0; j < 16; ++j) sum += f[j];
#pragma unroll
  for (int o = 16; o; o >>= 1) sum += __shfl_xor_sync(0xffffffffu, sum, o);
  const float mean = sum * (1.f / DM);
  float sq = 0.f;
#pragma unroll
  for (int j = 0; j < 16; ++j) { const float d = f[j] - mean; sq += d * d; }
#pragma unroll
  for (int o = 16; o; o >>= 1) sq += __shfl_xor_sync(0xffffffffu, sq, o);
  const float mb = rbf(mean), vb = rbf(sq * (1.f / DM));
  const float sd = rbf(sqrtf(rbf(vb + 1e-5f)));
  const float rinv = 1.f / sd;
  uint32_t o[8];
#pragma unroll
  for (int j = 0; j < 8; ++j) {
    const uint32_t d2 = pack_bf(f[2 * j] - mb, f[2 * j + 1] - mb);
    o[j] = pack_bf(bf_lo(d2) * rinv, bf_hi(d2) * rinv);
  }
  uint4* op = (uint4*)(g_xn + (size_t)row * DM);
  op[lane] = make_uint4(o[0], o[1], o[2], o[3]);
  op[32 + lane] = make_uint4(o[4], o[5], o[6], o[7]);
}

__global__ void __launch_bounds__(512, 1)
fused_kernel(const __grid_constant__ CUtensorMap tmBre, const __grid_constant__ CUtensorMap tmBim,
             const __grid_constant__ CUtensorMap tmW1, const __grid_constant__ CUtensorMap tmW2,
             const __grid_constant__ CUtensorMap tmCre, const __grid_constant__ CUtensorMap tmCim,
             const __grid_constant__ CUtensorMap tmXn,
             const bf16* __restrict__ x, const bf16* __restrict__ lam_re, const bf16* __restrict__ lam_im,
             const bf16* __restrict__ log_dt, const bf16* __restrict__ dskip, const bf16* __restrict__ b1,
             float* __restrict__ out) {
  extern __shared__ __align__(1024) unsigned char smem[];
  const uint32_t sb = smem_u32(smem);
  const int tid = threadIdx.x, lane = tid & 31, wg = tid >> 7;
  const int bid = blockIdx.x;
  const int r = bid & 7;
  const int rt = bid >> 3;
  const int row0 = rt * BM;
  const int fstart = 8 * ((43 * r) >> 1), fw = 168 + 8 * (r & 1);
  const uint32_t bar_full = sb + OFF_BARS, bar_empty = bar_full + 32, bar_x = bar_full + 64, bar_full2 = bar_full + 128, bar_empty2 = bar_full + 168;

  auto produce1 = [&](int it) {
    const int s = it % NST;
    const uint32_t slot = sb + OFF_RING + s * SLOT, bar = bar_full + 8 * s;
    mbar_expect_tx(bar, 20480);
    tma_2d(slot, &tmBre, 32 * it, CHN * r, bar);
    tma_2d(slot + 4096, &tmBim, 32 * it, CHN * r, bar);
    tma_2d(slot + 8192, &tmW1, fstart, 32 * it, bar);
    tma_2d(slot + 12288, &tmW1, fstart + 64, 32 * it, bar);
    tma_2d(slot + 16384, &tmW1, fstart + 128, 32 * it, bar);
  };
  if (tid == 0) {
    TSTAMP(0);
    for (int i = 0; i < NST; ++i) { mbar_init(bar_full + 8 * i, 1); mbar_init(bar_empty + 8 * i, 2); }
    for (int i = 0; i < NST2; ++i) { mbar_init(bar_full2 + 8 * i, 1); mbar_init(bar_empty2 + 8 * i, 2); }
    for (int i = 0; i < 8; ++i) mbar_init(bar_x + 8 * i, 1);
    asm volatile("fence.mbarrier_init.release.cluster;" ::: "memory");
    produce1(0); produce1(1);
    asm volatile("griddepcontrol.wait;" ::: "memory");
    fence_async_all();
    TSTAMP(7);
    for (int kb = 0; kb < 8; ++kb) {
      mbar_expect_tx(bar_x + 8 * kb, 16384);
      tma_2d(sb + OFF_X + kb * 16384, &tmXn, 64 * kb, row0, bar_x + 8 * kb);
      if (kb == 1) { produce1(2); produce1(3); }
    }
  } else if (tid == 32) {
    *(volatile unsigned*)(smem + OFF_EPOCH) = g_epoch[bid] + 1;
  } else if (tid >= 64 && tid < 71) {
    const CUtensorMap* tm = tid == 64 ? &tmXn : tid == 65 ? &tmBre : tid == 66 ? &tmBim : tid == 67 ? &tmW1 : tid == 68 ? &tmW2 : tid == 69 ? &tmCre : &tmCim;
    asm volatile("prefetch.tensormap [%0];" ::"l"((uint64_t)tm) : "memory");
  }
  __syncthreads();
  const unsigned epoch = *(volatile unsigned*)(smem + OFF_EPOCH);
  const uint32_t par = epoch & 1u;
  if (wg == 0) {
    asm volatile("setmaxnreg.dec.sync.aligned.u32 24;");
    if (tid == 0) {
      for (int it = NST; it < 16; ++it) {
        mbar_wait(bar_empty + 8 * (it % NST), ((it / NST) - 1) & 1);
        produce1(it);
      }
      for (int s = 0; s < NST; ++s) mbar_wait(bar_empty + 8 * s, 1);
      for (int it = 0; it < 16; ++it) {
        const int s = it % NST2;
        if (it >= NST2) mbar_wait(bar_empty2 + 8 * s, ((it / NST2) - 1) & 1);
        const uint32_t slot = sb + OFF_RING2 + s * SLOT2, bar = bar_full2 + 8 * s;
        const bool isF = (it < 6) ? (it < 3) : !(it & 1);
        const int p = (it < 6) ? (it % 3) : (it >> 1);
        const int oc = 64 * ((r + 1 + p) & 7);
        if (isF) {
          mbar_expect_tx(bar, 24576);
          for (int b = 0; b < 3; ++b) tma_2d(slot + 8192 * b, &tmW2, oc, fstart + 64 * b, bar);
        } else {
          mbar_expect_tx(bar, 16384);
          tma_2d(slot, &tmCre, CHN * r, oc, bar);
          tma_2d(slot + 8192, &tmCim, CHN * r, oc, bar);
        }
      }
    }
  } else if (wg == 1) {
    asm volatile("setmaxnreg.dec.sync.aligned.u32 72;");
    const int t = tid - 128, ch = t & 63, half = t >> 6;
    float2 lb;
    {
      const int p = CHN * r + ch;
      const float lre = __bfloat162float(lam_re[p]), lim = __bfloat162float(lam_im[p]);
      const float dt = rbf(expf(__bfloat162float(log_dt[p])));
      const float er = expf(dt * lre);
      float sn, cs; sincosf(dt * lim, &sn, &cs);
      lb = make_float2(er * cs, er * sn);
      const float nr = lb.x - 1.f, ni = lb.y, den = lre * lre + lim * lim;
      if (half == 0) {
        ((float2*)(smem + OFF_CC))[ch] = make_float2(2.f * (nr * lre + ni * lim) / den, 2.f * (ni * lre - nr * lim) / den);
        ((float2*)(smem + OFF_LB))[ch] = lb;
      }
      for (int c = t; c < FFP; c += 128) ((float*)(smem + OFF_B1))[c] = (c < fw) ? __bfloat162float(b1[fstart + c]) : 0.f;
    }
    bar_arrive<8, 384>();
    float2 p32 = lb;
#pragma unroll
    for (int i = 0; i < 5; ++i) p32 = make_float2(p32.x * p32.x - p32.y * p32.y, 2.f * p32.x * p32.y);
    const float2 p64 = make_float2(p32.x * p32.x - p32.y * p32.y, 2.f * p32.x * p32.y);
    const float2 p128 = make_float2(p64.x * p64.x - p64.y * p64.y, 2.f * p64.x * p64.y);
    bar_sync<1, 384>();
    float2 e0;
    {
      const float2* es = (const float2*)(smem + OFF_E0);
      const float2 s0 = es[ch], s1 = es[64 + ch], s2 = es[128 + ch], s3 = es[192 + ch];
      e0 = make_float2(p32.x * s0.x - p32.y * s0.y + s1.x, p32.x * s0.y + p32.y * s0.x + s1.y);
      if (half == 1) {
        const float ar = p32.x * s2.x - p32.y * s2.y + s3.x, ai = p32.x * s2.y + p32.y * s2.x + s3.y;
        const float er = p64.x * e0.x - p64.y * e0.y + ar, ei = p64.x * e0.y + p64.y * e0.x + ai;
        asm volatile("st.relaxed.gpu.global.v2.u32 [%0], {%1,%2};" ::"l"(&g_E[rt * 512 + CHN * r + ch]),
                     "r"((__float_as_uint(er) & 0xFFFFFFFEu) | par), "r"((__float_as_uint(ei) & 0xFFFFFFFEu) | par) : "memory");
      }
    }
    if (t == 0) TSTAMP(16);
    float Hr = 0.f, Hi = 0.f;
    {
      const int j0 = 8 * half, n = min(max(rt - j0, 0), 8);
      uint2 e[8];
      uint32_t pending = (1u << n) - 1u, itc = 0;
      const float2* ep = &g_E[j0 * 512 + CHN * r + ch];
      while (pending) {
#pragma unroll
        for (int j = 0; j < 8; ++j)
          if (pending & (1u << j))
            asm volatile("ld.relaxed.gpu.global.v2.u32 {%0,%1}, [%2];" : "=r"(e[j].x), "=r"(e[j].y) : "l"(ep + j * 512) : "memory");
#pragma unroll
        for (int j = 0; j < 8; ++j)
          if ((pending & (1u << j)) && (((e[j].x ^ par) | (e[j].y ^ par)) & 1u) == 0u) pending &= ~(1u << j);
        if (pending) { if (++itc > (1u << 22)) __trap(); }
      }
#pragma unroll
      for (int j = 0; j < 8; ++j) {
        if (j < n) {
          const float nr = p128.x * Hr - p128.y * Hi + __uint_as_float(e[j].x), ni = p128.x * Hi + p128.y * Hr + __uint_as_float(e[j].y);
          Hr = nr; Hi = ni;
        }
      }
      float2* hx = (float2*)(smem + OFF_E0 + 2048);
      if (half == 1) hx[ch] = make_float2(Hr, Hi);
      bar_sync<3, 128>();
      if (half == 0) {
        const float2 h1 = hx[ch];
        for (int j = 8; j < rt; ++j) { const float nr = p128.x * Hr - p128.y * Hi, ni = p128.x * Hi + p128.y * Hr; Hr = nr; Hi = ni; }
        Hr += h1.x; Hi += h1.y;
        float2* es = (float2*)(smem + OFF_E0);
#pragma unroll
        for (int k = 0; k < 4; ++k) {
          const float2 sk = es[64 * k + ch];
          es[64 * k + ch] = make_float2(Hr, Hi);
          const float nr = p32.x * Hr - p32.y * Hi + sk.x, ni = p32.x * Hi + p32.y * Hr + sk.y;
          Hr = nr; Hi = ni;
        }
      }
    }
    bar_arrive<2, 384>();
    if (t == 0) TSTAMP(17);
    bar_sync<7, 384>();
    asm volatile("griddepcontrol.wait;" ::: "memory");
#pragma unroll 1
    for (int sl = 0; sl < 2; ++sl) {
      const int slot = t + 128 * sl;
      const int lw = slot >> 5, ll = slot & 31;
      const int rowa = row0 + 16 * lw + (ll >> 2);
      const int colb = 64 * r + 2 * (ll & 3);
      float sum[32];
#pragma unroll
      for (int j = 0; j < 8; ++j) {
        const uint32_t dv = __ldg((const uint32_t*)(dskip + colb + 8 * j));
#pragma unroll
        for (int hh = 0; hh < 2; ++hh) {
          const size_t idx = (size_t)(rowa + 8 * hh) * DM + colb + 8 * j;
          const uint32_t xv = __ldg((const uint32_t*)(x + idx));
          uint32_t nv; asm volatile("ld.relaxed.gpu.global.u32 %0, [%1];" : "=r"(nv) : "l"(g_xn + idx) : "memory");
          const uint32_t p2 = pack_bf(bf_lo(nv) * bf_lo(dv), bf_hi(nv) * bf_hi(dv));
          sum[4 * j + 2 * hh] = bf_lo(xv) + bf_lo(p2);
          sum[4 * j + 2 * hh + 1] = bf_hi(xv) + bf_hi(p2);
        }
      }
      float4* sp = (float4*)(smem + OFF_SUM) + slot;
#pragma unroll
      for (int i = 0; i < 8; ++i) sp[256 * i] = make_float4(sum[4 * i], sum[4 * i + 1], sum[4 * i + 2], sum[4 * i + 3]);
    }
    bar_arrive<5, 384>();
    if (t == 0) { TSTAMP(20); g_epoch[bid] = epoch; }
  } else {
    asm volatile("setmaxnreg.inc.sync.aligned.u32 208;");
    const int w = wg - 2;
    const int wtid = tid & 127, wwarp = wtid >> 5;
    const int g = lane >> 2, qd = lane & 3;
    uint32_t af[44];
    {
      float accS[64], accF[88];
      for (int ks = 0; ks < 16; ++ks) {
        const int s = ks % NST;
        const uint32_t slot = sb + OFF_RING + s * SLOT;
        if (!(ks & 1)) mbar_wait(bar_x + 4 * ks, 0);
        mbar_wait(bar_full + 8 * s, (ks / NST) & 1);
        wg_fence();
#pragma unroll
        for (int kk = 0; kk < 2; ++kk) {
          const uint64_t da = mk_desc(sb + OFF_X + (ks >> 1) * 16384 + w * 8192 + (ks & 1) * 64 + kk * 32, 16, 1024, 1);
          const uint64_t dbs = mk_desc(slot + kk * 32, 16, 512, 2);
          const uint64_t dbf = mk_desc(slot + 8192 + kk * 2048, 4096, 1024, 1);
          const int sc = (ks | kk) ? 1 : 0;
          wgmma_n128<0, 1>(accS, da, dbs, sc);
          wgmma_n176<1, 1>(accF, da, dbf, sc);
        }
        wg_commit();
        if (ks > 0) {
          wg_wait<1>();
          if (wtid == 0) mbar_arrive(bar_empty + 8 * ((ks - 1) % NST));
        }
      }
      wg_wait<0>();
      if (wtid == 0) mbar_arrive(bar_empty + 8 * 3);
      if (tid == 256) TSTAMP(2);
      bar_sync<8, 384>();
      bar_sync<4, 256>();
      {
        const float2* cc = (const float2*)(smem + OFF_CC);
#pragma unroll
        for (int j = 0; j < 8; ++j) {
          const int ch = 8 * j + 2 * qd;
          const float4 c01 = *(const float4*)(cc + ch);
#pragma unroll
          for (int hh = 0; hh < 2; ++hh) {
            const int row = 64 * w + 16 * wwarp + g + 8 * hh;
            const float ur0 = accS[4 * j + 2 * hh], ur1 = accS[4 * j + 2 * hh + 1];
            const float ui0 = accS[32 + 4 * j + 2 * hh], ui1 = accS[32 + 4 * j + 2 * hh + 1];
            float4 o;
            o.x = c01.x * ur0 - c01.y * ui0; o.y = c01.x * ui0 + c01.y * ur0;
            o.z = c01.z * ur1 - c01.w * ui1; o.w = c01.z * ui1 + c01.w * ur1;
            *(float4*)(smem + OFF_BU + row * 512 + (((ch >> 1) ^ ((row & 1) << 2)) << 4)) = o;
          }
        }
      }
      bar_sync<4, 256>();
      {
        const int c = tid - 256, ch = c & 63, sub = c >> 6;
        const float2 lb = ((const float2*)(smem + OFF_LB))[ch];
        const unsigned char* bu = smem + OFF_BU + sub * 32 * 512 + ((ch & 1) << 3);
        float hr = 0.f, hi = 0.f;
#pragma unroll
        for (int i = 0; i < 32; ++i) {
          const float2 b = *(const float2*)(bu + i * 512 + (((ch >> 1) ^ ((i & 1) << 2)) << 4));
          const float nr = lb.x * hr - lb.y * hi + b.x, ni = lb.x * hi + lb.y * hr + b.y;
          hr = nr; hi = ni;
        }
        ((float2*)(smem + OFF_E0))[sub * 64 + ch] = make_float2(hr, hi);
      }
      bar_arrive<1, 384>();
      if (tid == 256) TSTAMP(3);
      {
        const float* b1s = (const float*)(smem + OFF_B1);
#pragma unroll
        for (int j = 0; j < 22; ++j) {
          const float2 bb = *(const float2*)(b1s + 8 * j + 2 * qd);
          const bool valid = (j < 21) || (r & 1);
#pragma unroll
          for (int hh = 0; hh < 2; ++hh) {
            const uint32_t a2 = mish2_pack(accF[4 * j + 2 * hh] + bb.x, accF[4 * j + 2 * hh + 1] + bb.y);
            af[2 * j + hh] = valid ? a2 : 0u;
          }
        }
      }
      if (tid == 256) TSTAMP(4);
    }
    uint32_t hf[32];
    float accA[32], accB[32], accC[32];
    int it = 0;
    auto release_prev = [&]() { if (wtid == 0) mbar_arrive(bar_empty2 + 8 * ((it - 1) % NST2)); };
    auto issueF = [&](float (&acc)[32]) {
      const uint32_t slot = sb + OFF_RING2 + (it % NST2) * SLOT2;
      mbar_wait(bar_full2 + 8 * (it % NST2), (it / NST2) & 1);
      wg_fence();
#pragma unroll
      for (int kk = 0; kk < 11; ++kk) wgmma_rs_n64<1, 1>(acc, af + 4 * kk, mk_desc(slot + kk * 2048, 8192, 1024, 1), kk ? 1 : 0);
      wg_commit();
    };
    auto issueS = [&](float (&acc)[32]) {
      const uint32_t slot = sb + OFF_RING2 + (it % NST2) * SLOT2;
      mbar_wait(bar_full2 + 8 * (it % NST2), (it / NST2) & 1);
      wg_fence();
#pragma unroll
      for (int kk = 0; kk < 4; ++kk) wgmma_rs_n64<0, 1>(acc, hf + 4 * kk, mk_desc(slot + kk * 32, 16, 1024, 1), 1);
#pragma unroll
      for (int kk = 0; kk < 4; ++kk) wgmma_rs_n64<0, -1>(acc, hf + 16 + 4 * kk, mk_desc(slot + 8192 + kk * 32, 16, 1024, 1), 1);
      wg_commit();
    };
    auto step = [&]() { wg_wait<1>(); release_prev(); ++it; };
    auto store_part = [&](const float (&acc)[32], int p) {
      uint4* dst = g_part + (((size_t)rt * 8 + ((r + 1 + p) & 7)) * 8 + r) * 1024 + (tid - 256);
#pragma unroll
      for (int v = 0; v < 4; ++v) {
        uint32_t wd[4];
#pragma unroll
        for (int k = 0; k < 4; ++k) wd[k] = (pack_bf(acc[8 * v + 2 * k], acc[8 * v + 2 * k + 1]) & 0xFFFFFFFEu) | par;
        asm volatile("st.global.v4.u32 [%0], {%1,%2,%3,%4};" ::"l"(dst + 256 * v), "r"(wd[0]), "r"(wd[1]), "r"(wd[2]), "r"(wd[3]) : "memory");
      }
    };
    issueF(accA); ++it;
    issueF(accB); ++it;
    issueF(accC); ++it;
    if (tid == 256) TSTAMP(5);
    bar_sync<2, 384>();
    {
      const int c = tid - 256, ch = c & 63, sub = c >> 6;
      const float2 lb = ((const float2*)(smem + OFF_LB))[ch];
      const float2 h0 = ((const float2*)(smem + OFF_E0))[sub * 64 + ch];
      const unsigned char* bu = smem + OFF_BU + sub * 32 * 512 + ((ch & 1) << 3);
      unsigned char* hp = smem + OFF_HP + sub * 32 * 128 + ((ch & 7) << 1);
      float hr = h0.x, hi = h0.y;
#pragma unroll 1
      for (int i0 = 0; i0 < 32; i0 += 8) {
        float2 b[8];
#pragma unroll
        for (int i = 0; i < 8; ++i) b[i] = *(const float2*)(bu + (i0 + i) * 512 + (((ch >> 1) ^ ((i & 1) << 2)) << 4));
#pragma unroll
        for (int i = 0; i < 8; ++i) {
          const float nr = lb.x * hr - lb.y * hi + b[i].x, ni = lb.x * hi + lb.y * hr + b[i].y;
          hr = nr; hi = ni;
          const uint32_t h2 = pack_bf(hr, hi);
          const int off = (i0 + i) * 128 + (((ch >> 3) ^ i) << 4);
          *(unsigned short*)(hp + off) = (unsigned short)(h2 & 0xFFFFu);
          *(unsigned short*)(hp + 16384 + off) = (unsigned short)(h2 >> 16);
        }
      }
    }
    bar_arrive<7, 384>();
    wg_wait<1>();
    if (wtid == 0) { mbar_arrive(bar_empty2); mbar_arrive(bar_empty2 + 8); }
    bar_sync<4, 256>();
#pragma unroll
    for (int kk = 0; kk < 8; ++kk) {
      const int row = 64 * w + 16 * wwarp + (lane & 7) + (lane & 8);
      const int chunk = 2 * (kk & 3) + (lane >> 4);
      const uint32_t a = sb + OFF_HP + (kk >> 2) * 16384 + row * 128 + ((chunk ^ (row & 7)) << 4);
      asm volatile("ldmatrix.sync.aligned.m8n8.x4.shared.b16 {%0,%1,%2,%3}, [%4];"
                   : "=r"(hf[4 * kk]), "=r"(hf[4 * kk + 1]), "=r"(hf[4 * kk + 2]), "=r"(hf[4 * kk + 3]) : "r"(a) : "memory");
    }
    if (tid == 256) TSTAMP(6);
    issueS(accA); step();
    issueS(accB); step(); store_part(accA, 0);
    issueS(accC); step(); store_part(accB, 1);
    if (tid == 256) TSTAMP(8);
    issueF(accA); step(); store_part(accC, 2);
    issueS(accA); step();
    issueF(accB); step(); store_part(accA, 3);
    issueS(accB); step();
    if (tid == 256) TSTAMP(10);
    issueF(accC); step(); store_part(accB, 4);
    issueS(accC); step();
    issueF(accA); step(); store_part(accC, 5);
    issueS(accA); step();
    if (tid == 256) TSTAMP(12);
    issueF(accB); step(); store_part(accA, 6);
    issueS(accB); step();
    const uint4* src = g_part + ((size_t)rt * 8 + r) * 8 * 1024 + (tid - 256);
    uint4 v[16];
#pragma unroll
    for (int k = 0; k < 4; ++k) {
      const uint4* p = src + (size_t)((r + 7 - k) & 7) * 1024;
#pragma unroll
      for (int i = 0; i < 4; ++i) v[4 * k + i] = ld_relaxed_v4(p + 256 * i);
    }
    wg_wait<0>();
    if (tid == 256) TSTAMP(14);
    float (&acc)[32] = accB;
    {
      const int rowa = row0 + 64 * w + 16 * wwarp + g;
      const int colb = 64 * r + 2 * qd;
      auto add4 = [&](const uint4* q4) {
#pragma unroll
        for (int i = 0; i < 4; ++i) {
          const uint4 q = q4[i];
          acc[8 * i + 0] += bf_lo(q.x & 0xFFFFFFFEu); acc[8 * i + 1] += bf_hi(q.x);
          acc[8 * i + 2] += bf_lo(q.y & 0xFFFFFFFEu); acc[8 * i + 3] += bf_hi(q.y);
          acc[8 * i + 4] += bf_lo(q.z & 0xFFFFFFFEu); acc[8 * i + 5] += bf_hi(q.z);
          acc[8 * i + 6] += bf_lo(q.w & 0xFFFFFFFEu); acc[8 * i + 7] += bf_hi(q.w);
        }
      };
      auto tag_bad = [&](const uint4* q4, int n) {
        uint32_t bad = 0;
#pragma unroll
        for (int i = 0; i < 16; ++i) if (i < n) bad |= (q4[i].x ^ par) | (q4[i].y ^ par) | (q4[i].z ^ par) | (q4[i].w ^ par);
        return bad & 1u;
      };
      uint32_t itc = 0;
      while (tag_bad(v, 16)) {
#pragma unroll
        for (int k = 0; k < 4; ++k) {
          const uint4* p = src + (size_t)((r + 7 - k) & 7) * 1024;
#pragma unroll
          for (int i = 0; i < 4; ++i) v[4 * k + i] = ld_relaxed_v4(p + 256 * i);
        }
        if (++itc > (1u << 22)) __trap();
      }
      uint4 u[12];
#pragma unroll
      for (int k = 0; k < 3; ++k) {
        const uint4* p = src + (size_t)((r + 3 - k) & 7) * 1024;
#pragma unroll
        for (int i = 0; i < 4; ++i) u[4 * k + i] = ld_relaxed_v4(p + 256 * i);
      }
#pragma unroll
      for (int k = 0; k < 4; ++k) add4(v + 4 * k);
#pragma unroll
      for (int k = 0; k < 3; ++k) {
        const uint4* p = src + (size_t)((r + 3 - k) & 7) * 1024;
        while (tag_bad(u + 4 * k, 4)) {
#pragma unroll
          for (int i = 0; i < 4; ++i) u[4 * k + i] = ld_relaxed_v4(p + 256 * i);
          if (++itc > (1u << 22)) __trap();
        }
        add4(u + 4 * k);
      }
      if (tid == 256) TSTAMP(24);
      bar_sync<5, 384>();
      const float4* sp = (const float4*)(smem + OFF_SUM) + (tid - 256);
#pragma unroll
      for (int j = 0; j < 8; ++j) {
        const float4 q = sp[256 * j];
        *(float2*)(out + (size_t)rowa * DM + colb + 8 * j) = make_float2(acc[4 * j] + q.x, acc[4 * j + 1] + q.y);
        *(float2*)(out + (size_t)(rowa + 8) * DM + colb + 8 * j) = make_float2(acc[4 * j + 2] + q.z, acc[4 * j + 3] + q.w);
      }
      if (tid == 256) TSTAMP(26);
    }
  }
}

typedef CUresult (*PFN_encodeTiled)(CUtensorMap*, CUtensorMapDataType, cuuint32_t, void*, const cuuint64_t*, const cuuint64_t*,
                                    const cuuint32_t*, const cuuint32_t*, CUtensorMapInterleave, CUtensorMapSwizzle,
                                    CUtensorMapL2promotion, CUtensorMapFloatOOBfill);

static void make_map(PFN_encodeTiled enc, CUtensorMap* m, const void* ptr, uint64_t inner, uint64_t outer, uint32_t binner,
                     uint32_t bouter, CUtensorMapSwizzle sw) {
  cuuint64_t dims[2] = {inner, outer};
  cuuint64_t strides[1] = {inner * 2};
  cuuint32_t box[2] = {binner, bouter};
  cuuint32_t es[2] = {1, 1};
  enc(m, CU_TENSOR_MAP_DATA_TYPE_BFLOAT16, 2, (void*)ptr, dims, strides, box, es,
      CU_TENSOR_MAP_INTERLEAVE_NONE, sw, CU_TENSOR_MAP_L2_PROMOTION_L2_256B, CU_TENSOR_MAP_FLOAT_OOB_FILL_NONE);
}

extern "C" void kernel_launch(void* const* d_in, const int* in_sizes, int n_in, void* d_out, int out_size) {
  static PFN_encodeTiled enc = nullptr;
  static void* p_xn = nullptr;
  if (!enc) {
    void* fn = nullptr;
    cudaDriverEntryPointQueryResult st;
    cudaGetDriverEntryPoint("cuTensorMapEncodeTiled", &fn, cudaEnableDefault, &st);
    enc = (PFN_encodeTiled)fn;
    cudaFuncSetAttribute(fused_kernel, cudaFuncAttributeMaxDynamicSharedMemorySize, SMEM_BYTES);
    cudaGetSymbolAddress(&p_xn, g_xn);
  }
  const bf16* x = (const bf16*)d_in[0];
  const bf16* lre = (const bf16*)d_in[1];
  const bf16* lim = (const bf16*)d_in[2];
  const bf16* Bre = (const bf16*)d_in[3];
  const bf16* Bim = (const bf16*)d_in[4];
  const bf16* Cre = (const bf16*)d_in[5];
  const bf16* Cim = (const bf16*)d_in[6];
  const bf16* ldt = (const bf16*)d_in[7];
  const bf16* dsk = (const bf16*)d_in[8];
  const bf16* w1 = (const bf16*)d_in[10];
  const bf16* b1 = (const bf16*)d_in[11];
  const bf16* w2 = (const bf16*)d_in[12];
  CUtensorMap mBre, mBim, mW1, mW2, mCre, mCim, mXn;
  make_map(enc, &mBre, Bre, DM, PS, 32, 64, CU_TENSOR_MAP_SWIZZLE_64B);
  make_map(enc, &mBim, Bim, DM, PS, 32, 64, CU_TENSOR_MAP_SWIZZLE_64B);
  make_map(enc, &mW1, w1, FF, DM, 64, 32, CU_TENSOR_MAP_SWIZZLE_128B);
  make_map(enc, &mW2, w2, DM, FF, 64, 64, CU_TENSOR_MAP_SWIZZLE_128B);
  make_map(enc, &mCre, Cre, PS, DM, 64, 64, CU_TENSOR_MAP_SWIZZLE_128B);
  make_map(enc, &mCim, Cim, PS, DM, 64, 64, CU_TENSOR_MAP_SWIZZLE_128B);
  make_map(enc, &mXn, p_xn, DM, 2048, 64, 128, CU_TENSOR_MAP_SWIZZLE_128B);
  ln_kernel<<<256, 256, 0, cudaStreamPerThread>>>(x);
  cudaLaunchConfig_t cfg = {};
  cfg.gridDim = dim3(128); cfg.blockDim = dim3(512); cfg.dynamicSmemBytes = SMEM_BYTES; cfg.stream = cudaStreamPerThread;
  cudaLaunchAttribute at[1];
  at[0].id = cudaLaunchAttributeProgrammaticStreamSerialization; at[0].val.programmaticStreamSerializationAllowed = 1;
  cfg.attrs = at; cfg.numAttrs = 1;
  cudaLaunchKernelEx(&cfg, fused_kernel, mBre, mBim, mW1, mW2, mCre, mCim, mXn, x, lre, lim, ldt, dsk, b1, (float*)d_out);
}
```
